```python
import torch

def _softmax(x, axis=-1):
    return torch.softmax(x, dim=axis)
def _gelu(x):
    return torch.nn.functional.gelu(x, approximate="tanh")
def _silu(x):
    return torch.nn.functional.silu(x)
def _sigmoid(x):
    return torch.sigmoid(x)
def _layernorm(x, axis=-1, eps=1e-5):
    m = x.mean(dim=axis, keepdim=True)
    v = x.var(dim=axis, keepdim=True, unbiased=False)
    return (x - m) / torch.sqrt(v + eps)
def _scatter_add(tgt, idx, src, axis=0):
    return tgt.clone().index_add_(axis, idx, src)
def _segment_sum(src, seg, n):
    out = torch.zeros((n,) + src.shape[1:], dtype=src.dtype)
    return out.index_add_(0, seg, src)
def _pad(x, pw):
    flat = tuple(v for pair in reversed(pw) for v in pair)
    return torch.nn.functional.pad(x, flat)

kernel_name = 'sequential_preLN__sliding_local_dilated__swiglu_ffn__prompt'

def setup_inputs():

    _w = (lambda a: (lambda t: t.to(torch.bfloat16) if t.is_floating_point() else t)(torch.as_tensor(a)))
    def _A_setup():
        B, S, D = 1, 2048, 512
        return {
            "x": _w((lambda *s: torch.randn(*s, dtype=torch.bfloat16) * 0.05)(B, S, D)),
            "wqkv": _w((lambda *s: torch.randn(*s, dtype=torch.bfloat16) * 0.05)(D, 3 * D)),
            "wo": _w((lambda *s: torch.randn(*s, dtype=torch.bfloat16) * 0.05)(D, D)),
        }
    _A_in = _A_setup()

    def _B_setup():
        B, S, D, F = 1, 2048, 512, 1792
        return {
            "x": _w((lambda *s: torch.randn(*s, dtype=torch.bfloat16) * 0.05)(B, S, D)),
            "w_gate": _w((lambda *s: torch.randn(*s, dtype=torch.bfloat16) * 0.05)(D, F)),
            "w_up": _w((lambda *s: torch.randn(*s, dtype=torch.bfloat16) * 0.05)(D, F)),
            "w_down": _w((lambda *s: torch.randn(*s, dtype=torch.bfloat16) * 0.05)(F, D)),
        }
    _B_in = _B_setup()

    return {
        "A_x": _A_in["x"],
        "A_wqkv": _A_in["wqkv"],
        "A_wo": _A_in["wo"],
        "B_x": _B_in["x"],
        "B_w_gate": _B_in["w_gate"],
        "B_w_up": _B_in["w_up"],
        "B_w_down": _B_in["w_down"],
    }

def reference(A_x, A_wqkv, A_wo, B_x, B_w_gate, B_w_up, B_w_down):
    def _A_ref(x, wqkv, wo):
        B, S, D = x.shape
        H = 32; Dh = D // H
        W, dil = 8, 2
        qkv = (lambda x, *d: x.permute(*d))((x @ wqkv).reshape(B, S, 3, H, Dh), 2, 0, 3, 1, 4)
        q, k, v = qkv[0], qkv[1], qkv[2]
        scale = Dh ** -0.5
        pos = torch.arange(S)
        off = torch.arange(W) * dil
        idx = pos[:, None] - off[None, :]
        mask = idx >= 0
        idx_c = torch.where(mask, idx, 0).reshape(-1)
        kg = k[:, :, idx_c, :].reshape(B, H, S, W, Dh)
        vg = v[:, :, idx_c, :].reshape(B, H, S, W, Dh)
        logits = torch.einsum("bhsd,bhswd->bhsw", q, kg) * scale
        logits = torch.where(mask[None, None, :, :], logits, -1e9)
        attn = _softmax(logits, axis=-1)
        o = torch.einsum("bhsw,bhswd->bhsd", attn, vg)
        return (lambda x, *d: x.permute(*d))(o, 0, 2, 1, 3).reshape(B, S, D) @ wo

    def _B_ref(x, w_gate, w_up, w_down):
        g = _silu(x @ w_gate)
        u = x @ w_up
        return (g * u) @ w_down

    x = A_x
    h = x + _A_ref(_layernorm(x, axis=-1), A_wqkv, A_wo)
    h2 = h + _B_ref(_layernorm(h, axis=-1), B_w_gate, B_w_up, B_w_down)
    return h2
```

```cpp
#include <cuda_runtime.h>
#include <cuda_bf16.h>
#include <cuda.h>
#include <stdint.h>

typedef __nv_bfloat16 bf16;

#define S_LEN 2048
#define DM 512
#define FF 1792

__device__ bf16 g_o[S_LEN * DM];
__device__ bf16 g_h[S_LEN * DM];
__device__ float2 g_stats[S_LEN * 8];
__device__ bf16 g_act[S_LEN * FF];

__device__ __forceinline__ uint32_t smem_u32(const void* p) { return (uint32_t)__cvta_generic_to_shared(p); }
__device__ __forceinline__ void mbar_init(uint32_t a, uint32_t c) {
  asm volatile("mbarrier.init.shared::cta.b64 [%0], %1;" ::"r"(a), "r"(c) : "memory");
}
__device__ __forceinline__ void mbar_expect_tx(uint32_t a, uint32_t b) {
  asm volatile("mbarrier.arrive.expect_tx.shared::cta.b64 _, [%0], %1;" ::"r"(a), "r"(b) : "memory");
}
__device__ __forceinline__ void mbar_arrive(uint32_t a) {
  asm volatile("mbarrier.arrive.shared::cta.b64 _, [%0];" ::"r"(a) : "memory");
}
__device__ __forceinline__ void mbar_arrive_remote(uint32_t a, uint32_t cta) {
  asm volatile(
      "{\n.reg .b32 ra;\nmapa.shared::cluster.u32 ra, %0, %1;\n"
      "mbarrier.arrive.shared::cluster.b64 _, [ra];\n}\n" ::"r"(a), "r"(cta)
      : "memory");
}
__device__ __forceinline__ bool mbar_try_wait(uint32_t a, uint32_t ph) {
  uint32_t ok;
  asm volatile(
      "{\n.reg .pred p;\nmbarrier.try_wait.parity.shared::cta.b64 p, [%1], %2;\nselp.u32 %0, 1, 0, p;\n}\n"
      : "=r"(ok)
      : "r"(a), "r"(ph)
      : "memory");
  return ok != 0;
}
__device__ __forceinline__ void mbar_wait(uint32_t a, uint32_t ph) {
  for (uint32_t it = 0; it < (1u << 22) && !mbar_try_wait(a, ph); ++it) {
  }
}
__device__ __forceinline__ void tma_load_2d(uint32_t dst, const CUtensorMap* tm, int c0, int c1, uint32_t bar) {
  asm volatile(
      "cp.async.bulk.tensor.2d.shared::cluster.global.mbarrier::complete_tx::bytes [%0], [%1, {%3, %4}], [%2];" ::"r"(dst),
      "l"((uint64_t)tm), "r"(bar), "r"(c0), "r"(c1)
      : "memory");
}
__device__ __forceinline__ void tma_load_2d_mc(uint32_t dst, const CUtensorMap* tm, int c0, int c1, uint32_t bar,
                                               uint16_t mask) {
  asm volatile(
      "cp.async.bulk.tensor.2d.shared::cluster.global.mbarrier::complete_tx::bytes.multicast::cluster [%0], [%1, {%3, "
      "%4}], [%2], %5;" ::"r"(dst),
      "l"((uint64_t)tm), "r"(bar), "r"(c0), "r"(c1), "h"(mask)
      : "memory");
}
__device__ __forceinline__ void prefetch_tmap(const CUtensorMap* tm) {
  asm volatile("prefetch.tensormap [%0];" ::"l"((uint64_t)tm) : "memory");
}
__device__ __forceinline__ void fence_proxy_async() { asm volatile("fence.proxy.async.shared::cta;" ::: "memory"); }
__device__ __forceinline__ void fence_mbar_init() { asm volatile("fence.mbarrier_init.release.cluster;" ::: "memory"); }
__device__ __forceinline__ void cluster_sync_relaxed() {
  asm volatile("barrier.cluster.arrive.relaxed.aligned;\nbarrier.cluster.wait.aligned;" ::: "memory");
}
__device__ __forceinline__ uint32_t cluster_rank() {
  uint32_t r;
  asm volatile("mov.u32 %0, %cluster_ctarank;" : "=r"(r));
  return r;
}
__device__ __forceinline__ void named_bar_sync(int id, int n) { asm volatile("bar.sync %0, %1;" ::"r"(id), "r"(n) : "memory"); }
__device__ __forceinline__ void wg_fence() { asm volatile("wgmma.fence.sync.aligned;" ::: "memory"); }
__device__ __forceinline__ void wg_commit() { asm volatile("wgmma.commit_group.sync.aligned;" ::: "memory"); }
template <int N>
__device__ __forceinline__ void wg_wait() {
  asm volatile("wgmma.wait_group.sync.aligned %0;" ::"n"(N) : "memory");
}
template <int R>
__device__ __forceinline__ void reg_inc() {
  asm volatile("setmaxnreg.inc.sync.aligned.u32 %0;" ::"n"(R));
}
template <int R>
__device__ __forceinline__ void reg_dec() {
  asm volatile("setmaxnreg.dec.sync.aligned.u32 %0;" ::"n"(R));
}

__device__ __forceinline__ uint64_t make_desc(uint32_t addr, uint32_t lbo_bytes, uint32_t sbo_bytes) {
  return (uint64_t)((addr & 0x3FFFF) >> 4) | ((uint64_t)(lbo_bytes >> 4) << 16) | ((uint64_t)(sbo_bytes >> 4) << 32) |
         (1ull << 62);
}
__device__ __forceinline__ uint32_t pack2(float a, float b) {
  __nv_bfloat162 v = __floats2bfloat162_rn(a, b);
  return *reinterpret_cast<uint32_t*>(&v);
}
__device__ __forceinline__ float lo_f(uint32_t u) { return __uint_as_float(u << 16); }
__device__ __forceinline__ float hi_f(uint32_t u) { return __uint_as_float(u & 0xFFFF0000u); }

__device__ __forceinline__ void sts128(uint32_t a, const uint4& v) {
  asm volatile("st.shared.v4.b32 [%0], {%1, %2, %3, %4};" ::"r"(a), "r"(v.x), "r"(v.y), "r"(v.z), "r"(v.w) : "memory");
}
__device__ __forceinline__ void sts32(uint32_t a, uint32_t v) { asm volatile("st.shared.b32 [%0], %1;" ::"r"(a), "r"(v) : "memory"); }
__device__ __forceinline__ void sts16(uint32_t a, uint16_t v) { asm volatile("st.shared.b16 [%0], %1;" ::"r"(a), "h"(v) : "memory"); }
__device__ __forceinline__ uint4 lds128(uint32_t a) {
  uint4 v;
  asm volatile("ld.shared.v4.b32 {%0, %1, %2, %3}, [%4];" : "=r"(v.x), "=r"(v.y), "=r"(v.z), "=r"(v.w) : "r"(a) : "memory");
  return v;
}
__device__ __forceinline__ float2 lds64f(uint32_t a) {
  float2 v;
  asm volatile("ld.shared.v2.f32 {%0, %1}, [%2];" : "=f"(v.x), "=f"(v.y) : "r"(a) : "memory");
  return v;
}
__device__ __forceinline__ void sts64f(uint32_t a, float x, float y) {
  asm volatile("st.shared.v2.f32 [%0], {%1, %2};" ::"r"(a), "f"(x), "f"(y) : "memory");
}
__device__ __forceinline__ float tanh_approx(float x) {
  float y;
  asm("tanh.approx.f32 %0, %1;" : "=f"(y) : "f"(x));
  return y;
}
__device__ __forceinline__ uint16_t bf16_bits(float x) {
  return __bfloat16_as_ushort(__float2bfloat16_rn(x));
}

#define TS(k, s, cond)

__device__ __forceinline__ void stsm4(uint32_t a, uint32_t r0, uint32_t r1, uint32_t r2, uint32_t r3) {
  asm volatile("stmatrix.sync.aligned.m8n8.x4.shared.b16 [%0], {%1, %2, %3, %4};" ::"r"(a), "r"(r0), "r"(r1), "r"(r2), "r"(r3) : "memory");
}
__device__ __forceinline__ void ldsm4(uint32_t a, uint32_t& r0, uint32_t& r1, uint32_t& r2, uint32_t& r3) {
  asm volatile("ldmatrix.sync.aligned.m8n8.x4.shared.b16 {%0, %1, %2, %3}, [%4];" : "=r"(r0), "=r"(r1), "=r"(r2), "=r"(r3) : "r"(a) : "memory");
}
__device__ __forceinline__ void tma_store_2d(const CUtensorMap* tm, uint32_t src, int c0, int c1) {
  asm volatile("cp.async.bulk.tensor.2d.global.shared::cta.bulk_group [%0, {%2, %3}], [%1];" ::"l"((uint64_t)tm), "r"(src), "r"(c0), "r"(c1) : "memory");
}
__device__ __forceinline__ void bulk_commit() { asm volatile("cp.async.bulk.commit_group;" ::: "memory"); }
__device__ __forceinline__ void bulk_wait_read0() { asm volatile("cp.async.bulk.wait_group.read 0;" ::: "memory"); }
__device__ __forceinline__ void bulk_wait0() { asm volatile("cp.async.bulk.wait_group 0;" ::: "memory"); }
__device__ __forceinline__ void unpack8(const uint4& v, float* f) {
  f[0] = lo_f(v.x); f[1] = hi_f(v.x); f[2] = lo_f(v.y); f[3] = hi_f(v.y);
  f[4] = lo_f(v.z); f[5] = hi_f(v.z); f[6] = lo_f(v.w); f[7] = hi_f(v.w);
}

template <int N>
__device__ __forceinline__ void fence_regs(float (&a)[N]) {
#pragma unroll
  for (int i = 0; i < N; i++) asm volatile("" : "+f"(a[i])::"memory");
}

__device__ unsigned int g_epoch;
__device__ unsigned int g_done;
__device__ unsigned int g_flag[5][16 * 32];
__device__ float2 g_csp[8][16][320];
__device__ __forceinline__ unsigned int ld_relaxed(const unsigned int* p) {
  unsigned int v;
  asm volatile("ld.relaxed.gpu.global.u32 %0, [%1];" : "=r"(v) : "l"(p) : "memory");
  return v;
}
__device__ __forceinline__ void flag_wait(const unsigned int* p, unsigned int target) {
  for (unsigned int it = 0; it < (1u << 22) && (int)(ld_relaxed(p) - target) < 0; ++it) {
  }
  asm volatile("fence.proxy.async.global;" ::: "memory");
}
__device__ __forceinline__ void flag_signal(unsigned int* p) {
  asm volatile("red.relaxed.gpu.global.add.u32 [%0], 1;" ::"l"(p) : "memory");
}
__device__ __forceinline__ void bulk_store_1d(void* gdst, uint32_t src, uint32_t bytes) {
  asm volatile("cp.async.bulk.global.shared::cta.bulk_group [%0], [%1], %2;" ::"l"(gdst), "r"(src), "r"(bytes) : "memory");
}
__device__ __forceinline__ float2 ldcg_f2(const float2* p) {
  float2 v;
  asm volatile("ld.global.cg.v2.f32 {%0, %1}, [%2];" : "=f"(v.x), "=f"(v.y) : "l"(p) : "memory");
  return v;
}

__device__ __forceinline__ void ldsm4t(uint32_t a, uint32_t& r0, uint32_t& r1, uint32_t& r2, uint32_t& r3) {
  asm volatile("ldmatrix.sync.aligned.m8n8.x4.trans.shared.b16 {%0, %1, %2, %3}, [%4];" : "=r"(r0), "=r"(r1), "=r"(r2), "=r"(r3) : "r"(a) : "memory");
}
__device__ __forceinline__ void mma16816(float (&c)[4], uint32_t a0, uint32_t a1, uint32_t a2, uint32_t a3, uint32_t b0, uint32_t b1) {
  asm volatile("mma.sync.aligned.m16n8k16.row.col.f32.bf16.bf16.f32 {%0,%1,%2,%3}, {%4,%5,%6,%7}, {%8,%9}, {%0,%1,%2,%3};"
               : "+f"(c[0]), "+f"(c[1]), "+f"(c[2]), "+f"(c[3])
               : "r"(a0), "r"(a1), "r"(a2), "r"(a3), "r"(b0), "r"(b1));
}

__device__ __forceinline__ void wgmma_ss_n16_ta1_tb0(float (&d)[8], uint64_t da, uint64_t db, int scale_d) {
  asm volatile("{\n.reg .pred p;\nsetp.ne.b32 p, %10, 0;\n"
    "wgmma.mma_async.sync.aligned.m64n16k16.f32.bf16.bf16 {%0, %1, %2, %3, %4, %5, %6, %7}, %8, %9, p, 1, 1, 1, 0;\n}\n"
    : "+f"(d[0]), "+f"(d[1]), "+f"(d[2]), "+f"(d[3]), "+f"(d[4]), "+f"(d[5]), "+f"(d[6]), "+f"(d[7])
    : "l"(da), "l"(db), "r"(scale_d));
}
__device__ __forceinline__ void wgmma_ss_n64_ta0_tb1(float (&d)[32], uint64_t da, uint64_t db, int scale_d) {
  asm volatile("{\n.reg .pred p;\nsetp.ne.b32 p, %34, 0;\n"
    "wgmma.mma_async.sync.aligned.m64n64k16.f32.bf16.bf16 {%0, %1, %2, %3, %4, %5, %6, %7, %8, %9, %10, %11, %12, %13, %14, %15, %16, %17, %18, %19, %20, %21, %22, %23, %24, %25, %26, %27, %28, %29, %30, %31}, %32, %33, p, 1, 1, 0, 1;\n}\n"
    : "+f"(d[0]), "+f"(d[1]), "+f"(d[2]), "+f"(d[3]), "+f"(d[4]), "+f"(d[5]), "+f"(d[6]), "+f"(d[7]), "+f"(d[8]), "+f"(d[9]), "+f"(d[10]), "+f"(d[11]), "+f"(d[12]), "+f"(d[13]), "+f"(d[14]), "+f"(d[15]), "+f"(d[16]), "+f"(d[17]), "+f"(d[18]), "+f"(d[19]), "+f"(d[20]), "+f"(d[21]), "+f"(d[22]), "+f"(d[23]), "+f"(d[24]), "+f"(d[25]), "+f"(d[26]), "+f"(d[27]), "+f"(d[28]), "+f"(d[29]), "+f"(d[30]), "+f"(d[31])
    : "l"(da), "l"(db), "r"(scale_d));
}
__device__ __forceinline__ void wgmma_ss_n112_ta0_tb1(float (&d)[56], uint64_t da, uint64_t db, int scale_d) {
  asm volatile("{\n.reg .pred p;\nsetp.ne.b32 p, %58, 0;\n"
    "wgmma.mma_async.sync.aligned.m64n112k16.f32.bf16.bf16 {%0, %1, %2, %3, %4, %5, %6, %7, %8, %9, %10, %11, %12, %13, %14, %15, %16, %17, %18, %19, %20, %21, %22, %23, %24, %25, %26, %27, %28, %29, %30, %31, %32, %33, %34, %35, %36, %37, %38, %39, %40, %41, %42, %43, %44, %45, %46, %47, %48, %49, %50, %51, %52, %53, %54, %55}, %56, %57, p, 1, 1, 0, 1;\n}\n"
    : "+f"(d[0]), "+f"(d[1]), "+f"(d[2]), "+f"(d[3]), "+f"(d[4]), "+f"(d[5]), "+f"(d[6]), "+f"(d[7]), "+f"(d[8]), "+f"(d[9]), "+f"(d[10]), "+f"(d[11]), "+f"(d[12]), "+f"(d[13]), "+f"(d[14]), "+f"(d[15]), "+f"(d[16]), "+f"(d[17]), "+f"(d[18]), "+f"(d[19]), "+f"(d[20]), "+f"(d[21]), "+f"(d[22]), "+f"(d[23]), "+f"(d[24]), "+f"(d[25]), "+f"(d[26]), "+f"(d[27]), "+f"(d[28]), "+f"(d[29]), "+f"(d[30]), "+f"(d[31]), "+f"(d[32]), "+f"(d[33]), "+f"(d[34]), "+f"(d[35]), "+f"(d[36]), "+f"(d[37]), "+f"(d[38]), "+f"(d[39]), "+f"(d[40]), "+f"(d[41]), "+f"(d[42]), "+f"(d[43]), "+f"(d[44]), "+f"(d[45]), "+f"(d[46]), "+f"(d[47]), "+f"(d[48]), "+f"(d[49]), "+f"(d[50]), "+f"(d[51]), "+f"(d[52]), "+f"(d[53]), "+f"(d[54]), "+f"(d[55])
    : "l"(da), "l"(db), "r"(scale_d));
}
__device__ __forceinline__ void wgmma_ss_n128_ta0_tb1(float (&d)[64], uint64_t da, uint64_t db, int scale_d) {
  asm volatile("{\n.reg .pred p;\nsetp.ne.b32 p, %66, 0;\n"
    "wgmma.mma_async.sync.aligned.m64n128k16.f32.bf16.bf16 {%0, %1, %2, %3, %4, %5, %6, %7, %8, %9, %10, %11, %12, %13, %14, %15, %16, %17, %18, %19, %20, %21, %22, %23, %24, %25, %26, %27, %28, %29, %30, %31, %32, %33, %34, %35, %36, %37, %38, %39, %40, %41, %42, %43, %44, %45, %46, %47, %48, %49, %50, %51, %52, %53, %54, %55, %56, %57, %58, %59, %60, %61, %62, %63}, %64, %65, p, 1, 1, 0, 1;\n}\n"
    : "+f"(d[0]), "+f"(d[1]), "+f"(d[2]), "+f"(d[3]), "+f"(d[4]), "+f"(d[5]), "+f"(d[6]), "+f"(d[7]), "+f"(d[8]), "+f"(d[9]), "+f"(d[10]), "+f"(d[11]), "+f"(d[12]), "+f"(d[13]), "+f"(d[14]), "+f"(d[15]), "+f"(d[16]), "+f"(d[17]), "+f"(d[18]), "+f"(d[19]), "+f"(d[20]), "+f"(d[21]), "+f"(d[22]), "+f"(d[23]), "+f"(d[24]), "+f"(d[25]), "+f"(d[26]), "+f"(d[27]), "+f"(d[28]), "+f"(d[29]), "+f"(d[30]), "+f"(d[31]), "+f"(d[32]), "+f"(d[33]), "+f"(d[34]), "+f"(d[35]), "+f"(d[36]), "+f"(d[37]), "+f"(d[38]), "+f"(d[39]), "+f"(d[40]), "+f"(d[41]), "+f"(d[42]), "+f"(d[43]), "+f"(d[44]), "+f"(d[45]), "+f"(d[46]), "+f"(d[47]), "+f"(d[48]), "+f"(d[49]), "+f"(d[50]), "+f"(d[51]), "+f"(d[52]), "+f"(d[53]), "+f"(d[54]), "+f"(d[55]), "+f"(d[56]), "+f"(d[57]), "+f"(d[58]), "+f"(d[59]), "+f"(d[60]), "+f"(d[61]), "+f"(d[62]), "+f"(d[63])
    : "l"(da), "l"(db), "r"(scale_d));
}
__device__ __forceinline__ void wgmma_ss_n192_ta0_tb1(float (&d)[96], uint64_t da, uint64_t db, int scale_d) {
  asm volatile("{\n.reg .pred p;\nsetp.ne.b32 p, %98, 0;\n"
    "wgmma.mma_async.sync.aligned.m64n192k16.f32.bf16.bf16 {%0, %1, %2, %3, %4, %5, %6, %7, %8, %9, %10, %11, %12, %13, %14, %15, %16, %17, %18, %19, %20, %21, %22, %23, %24, %25, %26, %27, %28, %29, %30, %31, %32, %33, %34, %35, %36, %37, %38, %39, %40, %41, %42, %43, %44, %45, %46, %47, %48, %49, %50, %51, %52, %53, %54, %55, %56, %57, %58, %59, %60, %61, %62, %63, %64, %65, %66, %67, %68, %69, %70, %71, %72, %73, %74, %75, %76, %77, %78, %79, %80, %81, %82, %83, %84, %85, %86, %87, %88, %89, %90, %91, %92, %93, %94, %95}, %96, %97, p, 1, 1, 0, 1;\n}\n"
    : "+f"(d[0]), "+f"(d[1]), "+f"(d[2]), "+f"(d[3]), "+f"(d[4]), "+f"(d[5]), "+f"(d[6]), "+f"(d[7]), "+f"(d[8]), "+f"(d[9]), "+f"(d[10]), "+f"(d[11]), "+f"(d[12]), "+f"(d[13]), "+f"(d[14]), "+f"(d[15]), "+f"(d[16]), "+f"(d[17]), "+f"(d[18]), "+f"(d[19]), "+f"(d[20]), "+f"(d[21]), "+f"(d[22]), "+f"(d[23]), "+f"(d[24]), "+f"(d[25]), "+f"(d[26]), "+f"(d[27]), "+f"(d[28]), "+f"(d[29]), "+f"(d[30]), "+f"(d[31]), "+f"(d[32]), "+f"(d[33]), "+f"(d[34]), "+f"(d[35]), "+f"(d[36]), "+f"(d[37]), "+f"(d[38]), "+f"(d[39]), "+f"(d[40]), "+f"(d[41]), "+f"(d[42]), "+f"(d[43]), "+f"(d[44]), "+f"(d[45]), "+f"(d[46]), "+f"(d[47]), "+f"(d[48]), "+f"(d[49]), "+f"(d[50]), "+f"(d[51]), "+f"(d[52]), "+f"(d[53]), "+f"(d[54]), "+f"(d[55]), "+f"(d[56]), "+f"(d[57]), "+f"(d[58]), "+f"(d[59]), "+f"(d[60]), "+f"(d[61]), "+f"(d[62]), "+f"(d[63]), "+f"(d[64]), "+f"(d[65]), "+f"(d[66]), "+f"(d[67]), "+f"(d[68]), "+f"(d[69]), "+f"(d[70]), "+f"(d[71]), "+f"(d[72]), "+f"(d[73]), "+f"(d[74]), "+f"(d[75]), "+f"(d[76]), "+f"(d[77]), "+f"(d[78]), "+f"(d[79]), "+f"(d[80]), "+f"(d[81]), "+f"(d[82]), "+f"(d[83]), "+f"(d[84]), "+f"(d[85]), "+f"(d[86]), "+f"(d[87]), "+f"(d[88]), "+f"(d[89]), "+f"(d[90]), "+f"(d[91]), "+f"(d[92]), "+f"(d[93]), "+f"(d[94]), "+f"(d[95])
    : "l"(da), "l"(db), "r"(scale_d));
}

#define XCH 18432
#define OFF_W 147456
#define OFF_T 212992
#define OFF_SST 229376
#define OFF_BAR 230528
#define OFF_CS3 227328
#define OFF_NST 145408
#define MEGA_SMEM (OFF_BAR + 768 + 1024)

__device__ __forceinline__ float swiglu(float g, float u) {
  const float hg = 0.5f * g;
  const float s = fmaf(hg, tanh_approx(hg), hg);
  return s * u;
}
__device__ __forceinline__ void arrive_both(uint32_t bar, uint32_t peer) {
  mbar_arrive(bar);
  mbar_arrive_remote(bar, peer);
}

struct TMaps {
  CUtensorMap x144, x64, wqkv, o, wo, h, g, u, act, actS, wd, out;
};

__global__ void __cluster_dims__(2, 1, 1) __launch_bounds__(384, 1)
    mega_kernel(const __grid_constant__ TMaps tm, float2* __restrict__ stats, const bf16* __restrict__ wqkv,
                const bf16* __restrict__ wgate, const bf16* __restrict__ wup) {
  extern __shared__ uint8_t smem_raw[];
  const uint32_t sb = (smem_u32(smem_raw) + 1023) & ~1023u;
  const uint32_t WR = sb + OFF_W;
  const uint32_t BAR = sb + OFF_BAR;
  const uint32_t zero_w = BAR + 8, full1 = BAR + 16, empty1 = BAR + 40, hs1 = BAR + 64;
  const uint32_t full2 = BAR + 72, x2full = BAR + 136, hs2 = BAR + 144;
  const uint32_t full3 = BAR + 152, empty3 = BAR + 184, afull3 = BAR + 216, nrdy3 = BAR + 280, hs3 = BAR + 344;
  const uint32_t full4 = BAR + 352, empty4 = BAR + 416, x4full = BAR + 480, xg = BAR + 488;
  const uint32_t p2done = BAR + 560;

  const int tid = threadIdx.x, warp = tid >> 5, lane = tid & 31;
  const int bid = blockIdx.x;
  const int rbA = bid & 15, cA = bid >> 4;
  const int rbB = bid >> 3, nt = bid & 7;
  const int rA0 = rbA * 128, rB0 = rbB * 128;
  const uint32_t crank = cluster_rank();
  const uint32_t peer = crank ^ 1;
  TS(0, 0, tid == 0);

  if (tid == 0) {
    for (int i = 0; i < 3; i++) mbar_init(xg + 8 * i, 1);
    fence_mbar_init();
#pragma unroll 1
    for (int g = 0; g < 3; g++) {
      mbar_expect_tx(xg + 8 * g, 8 * 6144);
#pragma unroll 1
      for (int c = 0; c < 8; c++)
        tma_load_2d(sb + c * XCH + g * 6144, &tm.x144, c * 64, rA0 - 16 + g * 48, xg + 8 * g);
    }
  } else if (tid == 32) {
    sts32(zero_w, 0u);
    for (int i = 0; i < 3; i++) {
      mbar_init(full1 + 8 * i, 1);
      mbar_init(empty1 + 8 * i, 16);
    }
    mbar_init(hs1, 16);
    for (int i = 0; i < 9; i++) mbar_init(full2 + 8 * i, 1);
    mbar_init(hs2, 16);
    for (int i = 0; i < 4; i++) {
      mbar_init(full3 + 8 * i, 1);
      mbar_init(empty3 + 8 * i, 16);
    }
    for (int i = 0; i < 8; i++) {
      mbar_init(afull3 + 8 * i, 1);
      mbar_init(full4 + 8 * i, 1);
      mbar_init(empty4 + 8 * i, 16);
    }
    mbar_init(nrdy3, 96);
    mbar_init(hs3, 2);
    mbar_init(x4full, 1);
    mbar_init(p2done, 2);
    fence_mbar_init();
  } else if (tid == 64) {
    const CUtensorMap* maps = &tm.x144;
#pragma unroll 1
    for (int i = 1; i < 12; i++) prefetch_tmap(maps + i);
  }
  const unsigned int ep = ld_relaxed(&g_epoch);
  __syncthreads();
  cluster_sync_relaxed();
  if (tid == 256) {
#pragma unroll 1
    for (int kc = 0; kc < 3; kc++) {
      mbar_expect_tx(full1 + 8 * kc, 24576);
      const uint32_t dst = WR + kc * 24576 + crank * 4096;
#pragma unroll
      for (int b = 0; b < 3; b++)
        tma_load_2d_mc(dst + b * 8192, &tm.wqkv, b * 512 + cA * 64, kc * 64 + crank * 32, full1 + 8 * kc, 3);
    }
  }

  __syncwarp();
  {
    const int c = lane & 7;
#pragma unroll 1
    for (int it = 0; it < 3; it++) {
      mbar_wait(xg + 8 * it, 0);
      const int row = (it * 12 + warp) * 4 + (lane >> 3);
      const uint32_t base = sb + c * XCH + row * 128;
      float f[64];
#pragma unroll
      for (int u = 0; u < 8; u++) unpack8(lds128(base + (((u + c) & 7) << 4)), f + 8 * u);
      float s0 = 0.f, s1 = 0.f, s2 = 0.f, s3 = 0.f;
#pragma unroll
      for (int i = 0; i < 64; i += 4) {
        s0 += f[i]; s1 += f[i + 1]; s2 += f[i + 2]; s3 += f[i + 3];
      }
      float s = (s0 + s1) + (s2 + s3);
      s += __shfl_xor_sync(0xffffffffu, s, 1);
      s += __shfl_xor_sync(0xffffffffu, s, 2);
      s += __shfl_xor_sync(0xffffffffu, s, 4);
      const float mean = s * (1.0f / DM);
      s0 = s1 = s2 = s3 = 0.f;
#pragma unroll
      for (int i = 0; i < 64; i += 4) {
        f[i] -= mean; f[i + 1] -= mean; f[i + 2] -= mean; f[i + 3] -= mean;
        s0 += f[i] * f[i]; s1 += f[i + 1] * f[i + 1]; s2 += f[i + 2] * f[i + 2]; s3 += f[i + 3] * f[i + 3];
      }
      s = (s0 + s1) + (s2 + s3);
      s += __shfl_xor_sync(0xffffffffu, s, 1);
      s += __shfl_xor_sync(0xffffffffu, s, 2);
      s += __shfl_xor_sync(0xffffffffu, s, 4);
      const float r = rsqrtf(s * (1.0f / DM) + 1e-5f);
#pragma unroll
      for (int u = 0; u < 8; u++) {
        uint4 w;
        w.x = pack2(f[8 * u] * r, f[8 * u + 1] * r);
        w.y = pack2(f[8 * u + 2] * r, f[8 * u + 3] * r);
        w.z = pack2(f[8 * u + 4] * r, f[8 * u + 5] * r);
        w.w = pack2(f[8 * u + 6] * r, f[8 * u + 7] * r);
        sts128(base + (((u + c) & 7) << 4), w);
      }
    }
  }
  fence_proxy_async();
  __syncthreads();
  TS(0, 1, tid == 0);

  if (warp >= 8) {
    reg_dec<56>();
    if (warp > 8) {
      const int t = tid - 288;
#pragma unroll 1
      for (int p = 96 + t; p < 320; p += 96) {
        const bf16* src;
        int ld;
        if (p < 96) { src = wqkv + (p >> 5) * 512 + cA * 64 + (p & 31) * 2; ld = 3 * DM; }
        else if (p < 208) { src = wgate + cA * 224 + (p - 96) * 2; ld = FF; }
        else { src = wup + cA * 224 + (p - 208) * 2; ld = FF; }
        src += (size_t)(32 * rbA) * ld;
        uint32_t v[32];
#pragma unroll
        for (int k = 0; k < 32; k++) v[k] = __ldg(reinterpret_cast<const uint32_t*>(src + (size_t)k * ld));
        float s0 = 0.f, s1 = 0.f;
#pragma unroll
        for (int k = 0; k < 32; k++) {
          s0 += lo_f(v[k]);
          s1 += hi_f(v[k]);
        }
        g_csp[cA][rbA][p] = make_float2(s0, s1);
      }
      __threadfence();
      named_bar_sync(4, 96);
      if (t == 0) flag_signal(&g_flag[4][cA * 32]);
      mbar_wait(p2done, 0);
      flag_wait(&g_flag[4][cA * 32], (ep + 1) * 16);
#pragma unroll 1
      for (int p = 96 + t; p < 320; p += 96) {
        float s0 = 0.f, s1 = 0.f;
#pragma unroll
        for (int i = 0; i < 16; i++) {
          const float2 v = ldcg_f2(&g_csp[cA][i][p]);
          s0 += v.x;
          s1 += v.y;
        }
        sts64f(sb + OFF_CS3 + (p - 96) * 8, s0, s1);
      }
      flag_wait(&g_flag[1][rbA * 32], (ep + 1) * 16);
#pragma unroll 1
      for (int r = t; r < 128; r += 96) {
        const float2* sp = stats + rA0 + r;
        float2 p[8];
#pragma unroll
        for (int i = 0; i < 8; i++) p[i] = ldcg_f2(sp + i * S_LEN);
        const float mean = (((p[0].x + p[1].x) + (p[2].x + p[3].x)) + ((p[4].x + p[5].x) + (p[6].x + p[7].x))) * 0.125f;
        float m2 = 0.f, d = 0.f;
#pragma unroll
        for (int i = 0; i < 8; i++) {
          m2 += p[i].y;
          d += (p[i].x - mean) * (p[i].x - mean);
        }
        m2 += 64.f * d;
        const float nr = rsqrtf(m2 * (1.0f / DM) + 1e-5f);
        sts64f(sb + OFF_NST + r * 8, nr, -mean * nr);
      }
      mbar_arrive(nrdy3);
    } else if (lane == 0) {
      {
        int s = 0, ph = 0;
#pragma unroll 1
        for (int kc = 3; kc < 8; kc++) {
          mbar_wait(empty1 + 8 * s, ph);
          mbar_expect_tx(full1 + 8 * s, 24576);
          const uint32_t dst = WR + s * 24576 + crank * 4096;
#pragma unroll
          for (int b = 0; b < 3; b++)
            tma_load_2d_mc(dst + b * 8192, &tm.wqkv, b * 512 + cA * 64, kc * 64 + crank * 32, full1 + 8 * s, 3);
          if (++s == 3) { s = 0; ph ^= 1; }
        }
      }
      mbar_wait(empty1 + 8, 0);
#pragma unroll 1
      for (int kc = 0; kc < 8; kc++) {
        mbar_expect_tx(full2 + 8 * kc, 24576);
        tma_load_2d(WR + kc * 8192, &tm.wo, nt * 64, kc * 64, full2 + 8 * kc);
      }
      mbar_wait(hs1, 0);
      mbar_expect_tx(x2full, 16384);
      tma_load_2d(sb + OFF_T, &tm.x64, nt * 64, rB0, x2full);
      tma_load_2d(sb + OFF_T + 8192, &tm.x64, nt * 64, rB0 + 64, x2full);
      TS(1, 1, true);
      flag_wait(&g_flag[0][rbB * 32], (ep + 1) * 8);
      TS(1, 2, true);
#pragma unroll 1
      for (int kc = 0; kc < 8; kc++)
        tma_load_2d_mc(sb + kc * 16384 + crank * 8192, &tm.o, kc * 64, rB0 + crank * 64, full2 + 8 * kc, 3);
      mbar_wait(hs2, 0);
      {
        const CUtensorMap* tw = crank ? &tm.u : &tm.g;
        int s = 0, ph = 1;
#pragma unroll 1
        for (int it = 0; it < 32; it++) {
          if (it == 4) {
            TS(2, 1, true);
            flag_wait(&g_flag[1][rbA * 32], (ep + 1) * 16);
            TS(2, 2, true);
#pragma unroll 1
            for (int c = 0; c < 8; c++) {
              mbar_expect_tx(afull3 + 8 * c, 16384);
              tma_load_2d(sb + c * 16384, &tm.h, c * 64, rA0, afull3 + 8 * c);
              tma_load_2d(sb + c * 16384 + 8192, &tm.h, c * 64, rA0 + 64, afull3 + 8 * c);
            }
          }
          mbar_wait(empty3 + 8 * s, ph);
          mbar_expect_tx(full3 + 8 * s, 16384);
          const uint32_t dst = WR + s * 16384 + crank * 8192;
          const int col = cA * 224 + (it >> 4) * 112;
          const int kr = (it & 15) * 32;
          tma_load_2d_mc(dst, tw, col, kr, full3 + 8 * s, 3);
          tma_load_2d_mc(dst + 4096, tw, col + 64, kr, full3 + 8 * s, 3);
          if (++s == 4) { s = 0; ph ^= 1; }
        }
      }
      mbar_wait(empty3 + 24, 1);
#pragma unroll 1
      for (int kc = 0; kc < 8; kc++) {
        mbar_expect_tx(full4 + 8 * kc, 24576);
        tma_load_2d(WR + kc * 8192, &tm.wd, nt * 64, kc * 64, full4 + 8 * kc);
      }
      TS(3, 1, true);
      flag_wait(&g_flag[2][rbB * 32], (ep + 1) * 16);
      TS(3, 2, true);
#pragma unroll 1
      for (int kc = 0; kc < 8; kc++)
        tma_load_2d_mc(sb + kc * 16384 + crank * 8192, &tm.act, kc * 64, rB0 + crank * 64, full4 + 8 * kc, 3);
      mbar_wait(hs3, 0);
      mbar_expect_tx(x4full, 16384);
      tma_load_2d(sb + 131072, &tm.h, nt * 64, rB0, x4full);
      tma_load_2d(sb + 131072 + 8192, &tm.h, nt * 64, rB0 + 64, x4full);
      {
        int s = 0, ph = 0;
#pragma unroll 1
        for (int kc = 8; kc < FF / 64; kc++) {
          mbar_wait(empty4 + 8 * s, ph);
          mbar_expect_tx(full4 + 8 * s, 24576);
          tma_load_2d_mc(sb + s * 16384 + crank * 8192, &tm.act, kc * 64, rB0 + crank * 64, full4 + 8 * s, 3);
          tma_load_2d(WR + s * 8192, &tm.wd, nt * 64, kc * 64, full4 + 8 * s);
          if (++s == 8) { s = 0; ph ^= 1; }
        }
      }
      if (atomicAdd(&g_done, 1u) == (ep + 1) * 128 - 1) g_epoch = ep + 1;
    }
    __syncwarp();
    cluster_sync_relaxed();
  } else {
    reg_inc<224>();
    const int wg = warp >> 2;
    const int mrow = (warp & 3) * 16 + ((lane >> 3) & 1) * 8 + (lane & 7);
    const int mx = (lane >> 4) ^ (mrow & 7);
    {
      float acc[96];
      float hacc[8];
#pragma unroll
      for (int i = 0; i < 96; i++) acc[i] = 0.f;
#pragma unroll
      for (int i = 0; i < 8; i++) hacc[i] = 0.f;
      int s = 0, ph = 0, ps = 0;
#pragma unroll 1
      for (int kc = 0; kc < 8; kc++) {
        mbar_wait(full1 + 8 * s, ph);
        const uint32_t st = WR + s * 24576;
        const uint32_t xa = sb + kc * XCH;
        wg_fence();
#pragma unroll
        for (int k = 0; k < 4; k++) {
          wgmma_ss_n192_ta0_tb1(acc, make_desc(xa + 2048 + wg * 8192 + k * 32, 16, 1024),
                                make_desc(st + k * 2048, 8192, 1024), 1);
          wgmma_ss_n16_ta1_tb0(hacc, make_desc(st + (1 + wg) * 8192 + k * 2048, 8192, 1024),
                               make_desc(xa + k * 32, 16, 1024), 1);
        }
        wg_commit();
        wg_wait<1>();
        if (kc > 0 && lane == 0) arrive_both(empty1 + 8 * ps, peer);
        ps = s;
        if (++s == 3) { s = 0; ph ^= 1; }
      }
      wg_wait<0>();
      fence_regs(acc);
      fence_regs(hacc);
      if (lane == 0) arrive_both(empty1 + 8 * ps, peer);
      named_bar_sync(1, 256);
      TS(0, 2, tid == 0);
      {
        float z;
        asm volatile("ld.shared.f32 %0, [%1];" : "=f"(z) : "r"(zero_w) : "memory");
#pragma unroll
        for (int i = 0; i < 8; i++) hacc[i] += z;
      }
      const uint32_t Qs = sb;
      const uint32_t Ks = sb + 128 * 144;
      const uint32_t Vs = Ks + 144 * 144;
      {
        const int rA = wg * 64 + (warp & 3) * 16 + (lane >> 2);
        const uint32_t off = rA * 144 + (lane & 3) * 4;
#pragma unroll
        for (int i = 0; i < 8; i++) {
          sts32(Qs + off + i * 16, pack2(acc[4 * i], acc[4 * i + 1]));
          sts32(Qs + off + 8 * 144 + i * 16, pack2(acc[4 * i + 2], acc[4 * i + 3]));
          sts32(Ks + off + 16 * 144 + i * 16, pack2(acc[32 + 4 * i], acc[32 + 4 * i + 1]));
          sts32(Ks + off + 24 * 144 + i * 16, pack2(acc[32 + 4 * i + 2], acc[32 + 4 * i + 3]));
          sts32(Vs + off + 16 * 144 + i * 16, pack2(acc[64 + 4 * i], acc[64 + 4 * i + 1]));
          sts32(Vs + off + 24 * 144 + i * 16, pack2(acc[64 + 4 * i + 2], acc[64 + 4 * i + 3]));
        }
        const uint32_t Hs = wg == 0 ? Ks : Vs;
        const int col = (warp & 3) * 16 + (lane >> 2);
#pragma unroll
        for (int i = 0; i < 2; i++) {
          const int hr = 8 * i + 2 * (lane & 3);
          sts16(Hs + hr * 144 + col * 2, bf16_bits(hacc[4 * i]));
          sts16(Hs + (hr + 1) * 144 + col * 2, bf16_bits(hacc[4 * i + 1]));
          sts16(Hs + hr * 144 + (col + 8) * 2, bf16_bits(hacc[4 * i + 2]));
          sts16(Hs + (hr + 1) * 144 + (col + 8) * 2, bf16_bits(hacc[4 * i + 3]));
        }
      }
      named_bar_sync(1, 256);

      {
        const int head = warp >> 1, par = warp & 1;
        const int g = lane >> 2, c = lane & 3;
        const uint32_t hb = head * 32;
        const uint32_t OS = sb + 65536;
#pragma unroll 1
        for (int T = 0; T < 4; T++) {
          const int i0 = 16 * T;
          uint32_t q0, q1, q2, q3;
          ldsm4(Qs + (2 * (i0 + (lane & 7) + ((lane >> 3) & 1) * 8) + par) * 144 + hb + (lane >> 4) * 16, q0, q1, q2, q3);
          const uint32_t krow = 2 * i0 + par;
          float sc[3][4];
#pragma unroll
          for (int t3 = 0; t3 < 3; t3++) sc[t3][0] = sc[t3][1] = sc[t3][2] = sc[t3][3] = 0.f;
          {
            uint32_t b0, b1, b2, b3;
            ldsm4(Ks + (krow + 2 * (8 * (lane >> 4) + (lane & 7))) * 144 + hb + ((lane >> 3) & 1) * 16, b0, b1, b2, b3);
            mma16816(sc[0], q0, q1, q2, q3, b0, b1);
            mma16816(sc[1], q0, q1, q2, q3, b2, b3);
            ldsm4(Ks + (krow + 2 * (16 + (lane & 7))) * 144 + hb + ((lane >> 3) & 1) * 16, b0, b1, b2, b3);
            mma16816(sc[2], q0, q1, q2, q3, b0, b1);
          }
          const int jmin = (rA0 == 0 && T == 0) ? 8 : 0;
          float m0 = -1e30f, m1 = -1e30f;
#pragma unroll
          for (int t3 = 0; t3 < 3; t3++) {
#pragma unroll
            for (int e = 0; e < 2; e++) {
              const int j = 8 * t3 + 2 * c + e;
              const bool v0 = j >= g + 1 && j <= g + 8 && j >= jmin;
              const bool v1 = j >= g + 9 && j <= g + 16;
              sc[t3][e] = v0 ? sc[t3][e] * 0.25f : -1e30f;
              sc[t3][2 + e] = v1 ? sc[t3][2 + e] * 0.25f : -1e30f;
              m0 = fmaxf(m0, sc[t3][e]);
              m1 = fmaxf(m1, sc[t3][2 + e]);
            }
          }
          m0 = fmaxf(m0, __shfl_xor_sync(0xffffffffu, m0, 1));
          m1 = fmaxf(m1, __shfl_xor_sync(0xffffffffu, m1, 1));
          m0 = fmaxf(m0, __shfl_xor_sync(0xffffffffu, m0, 2));
          m1 = fmaxf(m1, __shfl_xor_sync(0xffffffffu, m1, 2));
          float s0 = 0.f, s1 = 0.f;
#pragma unroll
          for (int t3 = 0; t3 < 3; t3++) {
#pragma unroll
            for (int e = 0; e < 2; e++) {
              sc[t3][e] = __expf(sc[t3][e] - m0);
              sc[t3][2 + e] = __expf(sc[t3][2 + e] - m1);
              s0 += sc[t3][e];
              s1 += sc[t3][2 + e];
            }
          }
          s0 += __shfl_xor_sync(0xffffffffu, s0, 1);
          s1 += __shfl_xor_sync(0xffffffffu, s1, 1);
          s0 += __shfl_xor_sync(0xffffffffu, s0, 2);
          s1 += __shfl_xor_sync(0xffffffffu, s1, 2);
          s0 = __frcp_rn(s0);
          s1 = __frcp_rn(s1);
          uint32_t p[3][2];
#pragma unroll
          for (int t3 = 0; t3 < 3; t3++) {
            p[t3][0] = pack2(sc[t3][0] * s0, sc[t3][1] * s0);
            p[t3][1] = pack2(sc[t3][2] * s1, sc[t3][3] * s1);
          }
          float oc[2][4];
#pragma unroll
          for (int d = 0; d < 2; d++) oc[d][0] = oc[d][1] = oc[d][2] = oc[d][3] = 0.f;
          {
            uint32_t b0, b1, b2, b3;
            ldsm4t(Vs + (krow + 2 * ((lane & 7) + ((lane >> 3) & 1) * 8)) * 144 + hb + (lane >> 4) * 16, b0, b1, b2, b3);
            mma16816(oc[0], p[0][0], p[0][1], p[1][0], p[1][1], b0, b1);
            mma16816(oc[1], p[0][0], p[0][1], p[1][0], p[1][1], b2, b3);
            ldsm4t(Vs + (krow + 2 * (16 + (lane & 7))) * 144 + hb + (lane >> 4) * 16, b0, b1, b2, b3);
            mma16816(oc[0], p[2][0], p[2][1], 0u, 0u, b0, b1);
            mma16816(oc[1], p[2][0], p[2][1], 0u, 0u, b2, b3);
          }
          const int ra = 2 * (i0 + g) + par, rb2 = ra + 16;
#pragma unroll
          for (int d = 0; d < 2; d++) {
            sts32(OS + ra * 128 + (((2 * head + d) ^ (ra & 7)) << 4) + c * 4, pack2(oc[d][0], oc[d][1]));
            sts32(OS + rb2 * 128 + (((2 * head + d) ^ (rb2 & 7)) << 4) + c * 4, pack2(oc[d][2], oc[d][3]));
          }
        }
      }
      fence_proxy_async();
      named_bar_sync(1, 256);
      if (tid == 0) {
        tma_store_2d(&tm.o, sb + 65536, cA * 64, rA0);
        tma_store_2d(&tm.o, sb + 65536 + 8192, cA * 64, rA0 + 64);
        bulk_commit();
        bulk_wait0();
        flag_signal(&g_flag[0][rbA * 32]);
      }
      if (lane == 0) arrive_both(hs1, peer);
      TS(0, 3, tid == 0);
    }
    {
      float acc[32];
#pragma unroll
      for (int i = 0; i < 32; i++) acc[i] = 0.f;
#pragma unroll 1
      for (int kc = 0; kc < 8; kc++) {
        mbar_wait(full2 + 8 * kc, 0);
        wg_fence();
#pragma unroll
        for (int k = 0; k < 4; k++)
          wgmma_ss_n64_ta0_tb1(acc, make_desc(sb + kc * 16384 + wg * 8192 + k * 32, 16, 1024),
                               make_desc(WR + kc * 8192 + k * 2048, 8192, 1024), 1);
        wg_commit();
      }
      mbar_wait(x2full, 0);
      wg_wait<0>();
      fence_regs(acc);
      if (lane == 0) arrive_both(hs2, peer);
      TS(1, 3, tid == 0);
      const uint32_t maddr = sb + OFF_T + wg * 8192 + mrow * 128;
      float sA = 0.f, sB = 0.f;
#pragma unroll
      for (int ip = 0; ip < 4; ip++) {
        const uint32_t ad = maddr + (((2 * ip) ^ mx) << 4);
        uint32_t x0, x1, x2, x3;
        ldsm4(ad, x0, x1, x2, x3);
        float* a = acc + 8 * ip;
        const uint32_t a0 = pack2(a[0], a[1]), a1 = pack2(a[2], a[3]), a2 = pack2(a[4], a[5]), a3 = pack2(a[6], a[7]);
        x0 = pack2(lo_f(x0) + lo_f(a0), hi_f(x0) + hi_f(a0));
        x1 = pack2(lo_f(x1) + lo_f(a1), hi_f(x1) + hi_f(a1));
        x2 = pack2(lo_f(x2) + lo_f(a2), hi_f(x2) + hi_f(a2));
        x3 = pack2(lo_f(x3) + lo_f(a3), hi_f(x3) + hi_f(a3));
        stsm4(ad, x0, x1, x2, x3);
        a[0] = lo_f(x0); a[1] = hi_f(x0); a[2] = lo_f(x1); a[3] = hi_f(x1);
        a[4] = lo_f(x2); a[5] = hi_f(x2); a[6] = lo_f(x3); a[7] = hi_f(x3);
        sA += (a[0] + a[1]) + (a[4] + a[5]);
        sB += (a[2] + a[3]) + (a[6] + a[7]);
      }
      sA += __shfl_xor_sync(0xffffffffu, sA, 1);
      sB += __shfl_xor_sync(0xffffffffu, sB, 1);
      sA += __shfl_xor_sync(0xffffffffu, sA, 2);
      sB += __shfl_xor_sync(0xffffffffu, sB, 2);
      const float mA = sA * (1.0f / 64), mB = sB * (1.0f / 64);
      float qA = 0.f, qB = 0.f;
#pragma unroll
      for (int i = 0; i < 8; i++) {
        float d;
        d = acc[4 * i] - mA; qA += d * d;
        d = acc[4 * i + 1] - mA; qA += d * d;
        d = acc[4 * i + 2] - mB; qB += d * d;
        d = acc[4 * i + 3] - mB; qB += d * d;
      }
      qA += __shfl_xor_sync(0xffffffffu, qA, 1);
      qB += __shfl_xor_sync(0xffffffffu, qB, 1);
      qA += __shfl_xor_sync(0xffffffffu, qA, 2);
      qB += __shfl_xor_sync(0xffffffffu, qB, 2);
      if ((lane & 3) == 0) {
        const uint32_t sp = sb + OFF_SST + (wg * 64 + (warp & 3) * 16 + (lane >> 2)) * 8;
        sts64f(sp, mA, qA);
        sts64f(sp + 64, mB, qB);
      }
      fence_proxy_async();
      named_bar_sync(2 + wg, 128);
      if ((tid & 127) == 0) {
        tma_store_2d(&tm.h, sb + OFF_T + wg * 8192, nt * 64, rB0 + wg * 64);
        bulk_store_1d(stats + nt * S_LEN + rB0 + wg * 64, sb + OFF_SST + wg * 512, 512);
        bulk_commit();
        bulk_wait0();
        flag_signal(&g_flag[1][rbB * 32]);
        mbar_arrive(p2done);
      }
      named_bar_sync(1, 256);
      TS(1, 4, tid == 0);
    }
    {
      float ga[56], ua[56];
      int s = 0, ph = 0, ps = 0;
      const uint32_t STG = wg ? sb + OFF_T : sb + 131072;
      const uint32_t saddr = STG + mrow * 224 + (lane >> 4) * 16;
#pragma unroll 1
      for (int pass = 0; pass < 2; pass++) {
#pragma unroll
        for (int i = 0; i < 56; i++) ga[i] = ua[i] = 0.f;
#pragma unroll 1
        for (int kh = 0; kh < 16; kh++) {
          if (pass == 0 && (kh & 1) == 0) {
            mbar_wait(afull3 + 4 * kh, 0);
            TS(2, 8 + (kh >> 1), tid == 0);
          }
          mbar_wait(full3 + 8 * s, ph);
          const uint32_t st = WR + s * 16384;
          const uint32_t aa = sb + wg * 8192 + (kh >> 1) * 16384 + (kh & 1) * 64;
          wg_fence();
#pragma unroll
          for (int k = 0; k < 2; k++) {
            const uint64_t da = make_desc(aa + k * 32, 16, 1024);
            wgmma_ss_n112_ta0_tb1(ga, da, make_desc(st + k * 2048, 4096, 1024), 1);
            wgmma_ss_n112_ta0_tb1(ua, da, make_desc(st + 8192 + k * 2048, 4096, 1024), 1);
          }
          wg_commit();
          wg_wait<1>();
          if (kh > 0 && lane == 0) arrive_both(empty3 + 8 * ps, peer);
          ps = s;
          if (++s == 4) { s = 0; ph ^= 1; }
        }
        wg_wait<0>();
        fence_regs(ga);
        fence_regs(ua);
        TS(2, 3 + 2 * pass, tid == 0);
        if (lane == 0) arrive_both(empty3 + 8 * ps, peer);
        if (pass == 1) {
          if ((tid & 127) == 0) bulk_wait_read0();
          named_bar_sync(2 + wg, 128);
        }
        mbar_wait(nrdy3, 0);
        {
          const int rl = wg * 64 + (warp & 3) * 16 + (lane >> 2);
          const float2 n0 = lds64f(sb + OFF_NST + rl * 8), n1 = lds64f(sb + OFF_NST + (rl + 8) * 8);
          const uint32_t csa = sb + OFF_CS3 + (pass * 56 + (lane & 3)) * 8;
#pragma unroll
          for (int ip = 0; ip < 7; ip++) {
            uint32_t w[4];
#pragma unroll
            for (int e = 0; e < 2; e++) {
              const float* g = ga + 8 * ip + 4 * e;
              const float* u = ua + 8 * ip + 4 * e;
              const float2 cg = lds64f(csa + (2 * ip + e) * 32), cu = lds64f(csa + 896 + (2 * ip + e) * 32);
              w[2 * e] = pack2(swiglu(fmaf(g[0], n0.x, n0.y * cg.x), fmaf(u[0], n0.x, n0.y * cu.x)),
                               swiglu(fmaf(g[1], n0.x, n0.y * cg.y), fmaf(u[1], n0.x, n0.y * cu.y)));
              w[2 * e + 1] = pack2(swiglu(fmaf(g[2], n1.x, n1.y * cg.x), fmaf(u[2], n1.x, n1.y * cu.x)),
                                   swiglu(fmaf(g[3], n1.x, n1.y * cg.y), fmaf(u[3], n1.x, n1.y * cu.y)));
            }
            stsm4(saddr + ip * 32, w[0], w[1], w[2], w[3]);
          }
        }
        fence_proxy_async();
        named_bar_sync(2 + wg, 128);
        if ((tid & 127) == 0) {
          tma_store_2d(&tm.actS, STG, cA * 224 + pass * 112, rA0 + wg * 64);
          bulk_commit();
        }
        TS(2, 4 + 2 * pass, tid == 0);
      }
      if ((tid & 127) == 0) {
        bulk_wait0();
        flag_signal(&g_flag[2][rbA * 32]);
        mbar_arrive(hs3);
      }
    }
    {
      float acc[32];
#pragma unroll
      for (int i = 0; i < 32; i++) acc[i] = 0.f;
      int s = 0, ph = 0, ps = 0;
#pragma unroll 1
      for (int kc = 0; kc < FF / 64; kc++) {
        mbar_wait(full4 + 8 * s, ph);
        wg_fence();
#pragma unroll
        for (int k = 0; k < 4; k++)
          wgmma_ss_n64_ta0_tb1(acc, make_desc(sb + s * 16384 + wg * 8192 + k * 32, 16, 1024),
                               make_desc(WR + s * 8192 + k * 2048, 8192, 1024), 1);
        wg_commit();
        wg_wait<1>();
        if (kc > 0 && lane == 0) arrive_both(empty4 + 8 * ps, peer);
        ps = s;
        if (++s == 8) { s = 0; ph ^= 1; }
      }
      mbar_wait(x4full, 0);
      wg_wait<0>();
      fence_regs(acc);
      TS(3, 3, tid == 0);
      const uint32_t maddr = sb + 131072 + wg * 8192 + mrow * 128;
#pragma unroll
      for (int ip = 0; ip < 4; ip++) {
        const uint32_t ad = maddr + (((2 * ip) ^ mx) << 4);
        uint32_t x0, x1, x2, x3;
        ldsm4(ad, x0, x1, x2, x3);
        const float* a = acc + 8 * ip;
        const uint32_t a0 = pack2(a[0], a[1]), a1 = pack2(a[2], a[3]), a2 = pack2(a[4], a[5]), a3 = pack2(a[6], a[7]);
        stsm4(ad, pack2(lo_f(x0) + lo_f(a0), hi_f(x0) + hi_f(a0)), pack2(lo_f(x1) + lo_f(a1), hi_f(x1) + hi_f(a1)),
              pack2(lo_f(x2) + lo_f(a2), hi_f(x2) + hi_f(a2)), pack2(lo_f(x3) + lo_f(a3), hi_f(x3) + hi_f(a3)));
      }
      fence_proxy_async();
      named_bar_sync(2 + wg, 128);
      if ((tid & 127) == 0) {
        tma_store_2d(&tm.out, sb + 131072 + wg * 8192, nt * 64, rB0 + wg * 64);
        bulk_commit();
        bulk_wait_read0();
      }
      TS(3, 4, tid == 0);
    }
    cluster_sync_relaxed();
  }
}

typedef CUresult (*PFN_encodeTiled)(CUtensorMap*, CUtensorMapDataType, cuuint32_t, void*, const cuuint64_t*,
                                    const cuuint64_t*, const cuuint32_t*, const cuuint32_t*, CUtensorMapInterleave,
                                    CUtensorMapSwizzle, CUtensorMapL2promotion, CUtensorMapFloatOOBfill);

static void make_tmap(PFN_encodeTiled fn, CUtensorMap* tm, const void* ptr, uint64_t cols, uint64_t rows,
                      uint32_t box_cols, uint32_t box_rows, bool swz = true) {
  cuuint64_t dims[2] = {cols, rows};
  cuuint64_t strides[1] = {cols * 2};
  cuuint32_t box[2] = {box_cols, box_rows};
  cuuint32_t es[2] = {1, 1};
  fn(tm, CU_TENSOR_MAP_DATA_TYPE_BFLOAT16, 2, const_cast<void*>(ptr), dims, strides, box, es,
     CU_TENSOR_MAP_INTERLEAVE_NONE, swz ? CU_TENSOR_MAP_SWIZZLE_128B : CU_TENSOR_MAP_SWIZZLE_NONE,
     CU_TENSOR_MAP_L2_PROMOTION_L2_256B, CU_TENSOR_MAP_FLOAT_OOB_FILL_NONE);
}

extern "C" void kernel_launch(void* const* d_in, const int* in_sizes, int n_in, void* d_out, int out_size) {
  const bf16* x = (const bf16*)d_in[0];
  const bf16* wqkv = (const bf16*)d_in[1];
  const bf16* wo = (const bf16*)d_in[2];
  const bf16* wg = (const bf16*)d_in[4];
  const bf16* wu = (const bf16*)d_in[5];
  const bf16* wd = (const bf16*)d_in[6];
  bf16* out = (bf16*)d_out;

  void* fnp = nullptr;
  cudaDriverEntryPointQueryResult qres;
  cudaGetDriverEntryPoint("cuTensorMapEncodeTiled", &fnp, cudaEnableDefault, &qres);
  PFN_encodeTiled fn = (PFN_encodeTiled)fnp;

  bf16 *po, *ph, *pact;
  float2* pst;
  cudaGetSymbolAddress((void**)&po, g_o);
  cudaGetSymbolAddress((void**)&ph, g_h);
  cudaGetSymbolAddress((void**)&pst, g_stats);
  cudaGetSymbolAddress((void**)&pact, g_act);

  TMaps tm;
  make_tmap(fn, &tm.x144, x, DM, S_LEN, 64, 48);
  make_tmap(fn, &tm.x64, x, DM, S_LEN, 64, 64);
  make_tmap(fn, &tm.wqkv, wqkv, 3 * DM, DM, 64, 32);
  make_tmap(fn, &tm.o, po, DM, S_LEN, 64, 64);
  make_tmap(fn, &tm.wo, wo, DM, DM, 64, 64);
  make_tmap(fn, &tm.h, ph, DM, S_LEN, 64, 64);
  make_tmap(fn, &tm.g, wg, FF, DM, 64, 32);
  make_tmap(fn, &tm.u, wu, FF, DM, 64, 32);
  make_tmap(fn, &tm.act, pact, FF, S_LEN, 64, 64);
  make_tmap(fn, &tm.actS, pact, FF, S_LEN, 112, 64, false);
  make_tmap(fn, &tm.wd, wd, DM, FF, 64, 64);
  make_tmap(fn, &tm.out, out, DM, S_LEN, 64, 64);

  cudaFuncSetAttribute(mega_kernel, cudaFuncAttributeMaxDynamicSharedMemorySize, MEGA_SMEM);
  mega_kernel<<<128, 384, MEGA_SMEM, cudaStreamPerThread>>>(tm, pst, wqkv, wg, wu);
}
```
